```python
import torch

def _softmax(x, axis=-1):
    return torch.softmax(x, dim=axis)
def _gelu(x):
    return torch.nn.functional.gelu(x, approximate="tanh")
def _silu(x):
    return torch.nn.functional.silu(x)
def _sigmoid(x):
    return torch.sigmoid(x)
def _layernorm(x, axis=-1, eps=1e-5):
    m = x.mean(dim=axis, keepdim=True)
    v = x.var(dim=axis, keepdim=True, unbiased=False)
    return (x - m) / torch.sqrt(v + eps)
def _scatter_add(tgt, idx, src, axis=0):
    return tgt.clone().index_add_(axis, idx, src)
def _segment_sum(src, seg, n):
    out = torch.zeros((n,) + src.shape[1:], dtype=src.dtype)
    return out.index_add_(0, seg, src)
def _pad(x, pw):
    flat = tuple(v for pair in reversed(pw) for v in pair)
    return torch.nn.functional.pad(x, flat)

kernel_name = 'concat_heads__grouped_kv_mqa__ssm_conv_s4d__prompt'

def setup_inputs():

    _w = (lambda a: (lambda t: t.to(torch.bfloat16) if t.is_floating_point() else t)(torch.as_tensor(a)))
    def _A_setup():
        B, S, D, H = 1, 2048, 512, 32
        Dh = D // H
        return {
            "x": _w((lambda *s: torch.randn(*s, dtype=torch.bfloat16) * 0.05)(B, S, D)),
            "wq": _w((lambda *s: torch.randn(*s, dtype=torch.bfloat16) * 0.8)(D, H * Dh)),
            "wk": _w((lambda *s: torch.randn(*s, dtype=torch.bfloat16) * 0.8)(D, Dh)),
            "wv": _w((lambda *s: torch.randn(*s, dtype=torch.bfloat16) * 0.05)(D, Dh)),
            "wo": _w((lambda *s: torch.randn(*s, dtype=torch.bfloat16) * 0.05)(H * Dh, D)),
        }
    _A_in = _A_setup()

    def _B_setup():
        Bsz, L, D, N = 1, 2048, 512, 128
        return {
            "u": _w((lambda *s: torch.randn(*s, dtype=torch.bfloat16) * 0.05)(Bsz, L, D)),
            "log_A_real": _w((lambda *s: torch.randn(*s, dtype=torch.bfloat16) * 6.4)(D, N) * 0.5),
            "A_imag": _w((lambda *s: torch.randn(*s, dtype=torch.bfloat16) * 0.05)(D, N) * 3.14),
            "C_real": _w((lambda *s: torch.randn(*s, dtype=torch.bfloat16) * 0.05)(D, N) / N ** 0.5),
            "C_imag": _w((lambda *s: torch.randn(*s, dtype=torch.bfloat16) * 0.05)(D, N) / N ** 0.5),
            "log_dt": _w((lambda *s: torch.randn(*s, dtype=torch.bfloat16) * 0.05)(D) * 0.5 - 4.0),
            "D_skip": _w((lambda *s: torch.randn(*s, dtype=torch.bfloat16) * 0.05)(D)),
        }
    _B_in = _B_setup()

    return {
        "A_x": _A_in["x"],
        "A_wq": _A_in["wq"],
        "A_wk": _A_in["wk"],
        "A_wv": _A_in["wv"],
        "A_wo": _A_in["wo"],
        "B_u": _B_in["u"],
        "B_log_A_real": _B_in["log_A_real"],
        "B_A_imag": _B_in["A_imag"],
        "B_C_real": _B_in["C_real"],
        "B_C_imag": _B_in["C_imag"],
        "B_log_dt": _B_in["log_dt"],
        "B_D_skip": _B_in["D_skip"],
    }

def reference(A_x, A_wq, A_wk, A_wv, A_wo, B_u, B_log_A_real, B_A_imag, B_C_real, B_C_imag, B_log_dt, B_D_skip):
    def _A_ref(x, wq, wk, wv, wo):
        B, S, D = x.shape
        H = 32
        Dh = D // H
        q = (lambda x, *d: x.permute(*d))((x @ wq).reshape(B, S, H, Dh), 0, 2, 1, 3)
        k = x @ wk
        v = x @ wv
        scores = torch.einsum("bhqd,bkd->bhqk", q, k) * (Dh ** -0.5)
        p = _softmax(scores, axis=-1)
        o = torch.einsum("bhqk,bkd->bhqd", p, v)
        return (lambda x, *d: x.permute(*d))(o, 0, 2, 1, 3).reshape(B, S, H * Dh) @ wo

    def _B_ref(u, log_A_real, A_imag, C_real, C_imag, log_dt, D_skip):
        L = u.shape[1]
        dt = torch.exp(log_dt)
        A = -torch.exp(log_A_real) + 1j * A_imag
        C = (C_real + 1j * C_imag) * dt[:, None]
        pos = (lambda x, dt: x.to(dt))(torch.arange(L), log_dt.dtype)
        P = torch.exp((A * dt[:, None])[:, :, None] * pos[None, None, :])
        K = 2.0 * torch.einsum("dn,dnl->dl", C, P).real
        L2 = 2 * L
        u_t = (lambda x, *d: x.permute(*d))(u, 0, 2, 1)
        Kf = (lambda x, *a, **k: torch.fft.rfft(x.float(), *a, **k))(K, L2)
        Uf = (lambda x, *a, **k: torch.fft.rfft(x.float(), *a, **k))(u_t, L2)
        y = (lambda x, *a, **k: torch.fft.irfft(x, *a, **k).to(torch.bfloat16))(Uf * Kf[None, :, :], L2)[:, :, :L]
        y = (lambda x, *d: x.permute(*d))(y, 0, 2, 1)
        return y + u * D_skip[None, None, :]

    a = _A_ref(A_x, A_wq, A_wk, A_wv, A_wo)
    b = _B_ref(B_u, B_log_A_real, B_A_imag, B_C_real, B_C_imag, B_log_dt, B_D_skip)
    return torch.concatenate([a, b], axis=-1)
```

```cpp
#include <cuda_runtime.h>
#include <cuda_bf16.h>
#include <cuda_fp16.h>
#include <cuda.h>
#include <stdint.h>

namespace {

constexpr int DM = 512;
constexpr int NCTA = 128;
constexpr int NCOMP = 512;
constexpr int NTHREADS = NCOMP + 128;

struct __align__(1024) Xchg {
  unsigned char Kimg[65536];
  unsigned char Vimg[70656];
  float stat[NCTA * 4];
  unsigned int oflag[2][NCTA];
  unsigned int uflag[NCTA];
  unsigned int yflag[NCTA];
  unsigned int epoch[NCTA];
  unsigned int pad[96];
  unsigned int bar;
};
__device__ Xchg g_x;
#define g_Kimg g_x.Kimg
#define g_Vimg g_x.Vimg
#define g_stat g_x.stat
#define g_oflag g_x.oflag
#define g_uflag g_x.uflag
#define g_yflag g_x.yflag
#define g_epoch g_x.epoch
#define g_bar g_x.bar
__device__ __align__(1024) unsigned char g_Oimg[32 * 65536];
__device__ __align__(1024) __nv_bfloat16 g_Y[512 * 2048];
__device__ __align__(1024) __nv_bfloat16 g_U[512 * 2048];

struct HIdx { unsigned short v[128 * 16]; };
constexpr int kappa_off_c(int p) {
  int lvl = p >= 1024 ? 3 : (p >= 512 ? 2 : (p >= 256 ? 1 : 0));
  int h = 8 * lvl + ((((p >> 7) << 3) + (p & 7)) >> lvl);
  return (h * 16 + ((p >> 3) & 15)) * 4;
}
constexpr HIdx make_hidx() {
  HIdx t{};
  const int base[8] = {0, 40, 56, 72, 87, 102, 114, 126};
  const int off[7] = {287, 95, 95, 87, 87, 79, 79};
  const int ntap[7] = {256, 65, 65, 64, 65, 64, 64};
  const int p0[7] = {0, 256, 258, 520, 516, 1040, 1032};
  const int st[7] = {1, 4, 4, 8, 8, 16, 16};
  for (int c = 0; c < 128; c++)
    for (int e = 0; e < 16; e++) {
      int v = 3072;
      for (int sg = 0; sg < 7; sg++)
        if (c >= base[sg] && c < base[sg + 1]) {
          int tap = off[sg] - (c - base[sg]) * 8 - e;
          if (tap >= 0 && tap < ntap[sg]) {
            int p = p0[sg] + st[sg] * tap;
            if (p == 514) p = 512;
            if (p == 1028) p = 1024;
            v = kappa_off_c(p);
          }
        }
      t.v[c * 16 + e] = (unsigned short)v;
    }
  return t;
}
__device__ __align__(16) const HIdx g_hidx = make_hidx();


constexpr int SM_K    = 0;
constexpr int SM_V    = 65536;
constexpr int SM_X    = 0;
constexpr int SM_RING = 65536;
constexpr int SM_JOB  = 136192;
constexpr int SM_U    = 179200;
constexpr int SM_WKV  = 197632;
constexpr int SM_Q    = 211968;
constexpr int SM_T    = 197632;
constexpr int SM_WQ4  = 205824;
constexpr int SM_STAT = 229376;
constexpr int SM_BAR  = 231424;
constexpr int SM_RED  = SM_BAR + 320;
constexpr int SM_TOTAL = SM_BAR + 512;
constexpr int U_STRIDE = 4608;
constexpr int SS_TA  = 0;
constexpr int SS_TB  = 27648;
constexpr int SS_X1E = 0;
constexpr int SS_X1O = 4096;
constexpr int SS_Y2E = 8192;
constexpr int SS_Y2O = 12416;
constexpr int SS_Y3E = 16640;
constexpr int SS_Y3O = 20736;
constexpr int SS_H   = 24832;
constexpr int SS_Y0  = 0;
constexpr int SS_Y1  = SS_Y0 + 8192;
constexpr int SS_Y2  = SS_Y1 + 7168;
constexpr int SS_Y3  = SS_Y2 + 6144;

enum { MB_X = 0, MB_EARLY = 1, MB_KVG = 2, MB_QDONE = 3, MB_ATT = 4, MB_OA = 5, MB_USTG = 6, MB_WQ = 8  , MB_KV0 = 16  ,
       MB_OB = 24, MB_O = 25  , MB_Y = 29, MB_UIN = 30, MB_UFREE = 31, MB_COUNT = 32 };

struct Params {
  const __nv_bfloat16* x;
  const __nv_bfloat16* wq;
  const __nv_bfloat16* wk;
  const __nv_bfloat16* wv;
  const __nv_bfloat16* log_A_real;
  const __nv_bfloat16* A_imag;
  const __nv_bfloat16* C_real;
  const __nv_bfloat16* C_imag;
  const __nv_bfloat16* log_dt;
  const __nv_bfloat16* D_skip;
  __nv_bfloat16* out;
};

__device__ __forceinline__ uint32_t smem_u32(const void* p) { return (uint32_t)__cvta_generic_to_shared(p); }
__device__ __forceinline__ void wg_fence() { asm volatile("wgmma.fence.sync.aligned;\n" ::: "memory"); }
__device__ __forceinline__ void wg_commit() { asm volatile("wgmma.commit_group.sync.aligned;\n" ::: "memory"); }
template <int N> __device__ __forceinline__ void wg_wait() { asm volatile("wgmma.wait_group.sync.aligned %0;\n" ::"n"(N) : "memory"); }
__device__ __forceinline__ void fence_async_smem() { asm volatile("fence.proxy.async.shared::cta;\n" ::: "memory"); }
__device__ __forceinline__ void bar_sync(int id, int n) { asm volatile("bar.sync %0, %1;\n" ::"r"(id), "r"(n) : "memory"); }
__device__ __forceinline__ bool bar_red_or(int id, int n, bool p) {
  uint32_t r;
  asm volatile("{\n.reg .pred p, q;\nsetp.ne.u32 p, %3, 0;\nbar.red.or.pred q, %1, %2, p;\nselp.u32 %0, 1, 0, q;\n}\n"
               : "=r"(r) : "r"(id), "r"(n), "r"((uint32_t)p) : "memory");
  return r != 0;
}
__device__ __forceinline__ uint64_t make_desc(uint32_t addr, uint32_t lbo, uint32_t sbo, uint32_t swz) {
  uint64_t d = 0;
  d |= (uint64_t)((addr & 0x3FFFF) >> 4);
  d |= (uint64_t)((lbo & 0x3FFFF) >> 4) << 16;
  d |= (uint64_t)((sbo & 0x3FFFF) >> 4) << 32;
  d |= (uint64_t)swz << 62;
  return d;
}
template <int N> __device__ __forceinline__ void fence_regs(float (&d)[N]) {
#pragma unroll
  for (int i = 0; i < N; i++) asm volatile("" : "+f"(d[i])::"memory");
}
__device__ __forceinline__ void mbar_init(uint32_t bar, uint32_t cnt) { asm volatile("mbarrier.init.shared::cta.b64 [%0], %1;\n" ::"r"(bar), "r"(cnt) : "memory"); }
__device__ __forceinline__ void mbar_expect_tx(uint32_t bar, uint32_t bytes) {
  asm volatile("mbarrier.arrive.expect_tx.shared::cta.b64 _, [%0], %1;\n" ::"r"(bar), "r"(bytes) : "memory");
}
__device__ __forceinline__ void mbar_arrive(uint32_t bar) { asm volatile("mbarrier.arrive.shared::cta.b64 _, [%0];\n" ::"r"(bar) : "memory"); }
__device__ __forceinline__ void mbar_wait(uint32_t bar, uint32_t parity) {
#pragma unroll 1
  for (uint32_t it = 0; it < (1u << 26); it++) {
    uint32_t ok;
    asm volatile("{\n.reg .pred p;\nmbarrier.try_wait.parity.shared::cta.b64 p, [%1], %2;\nselp.u32 %0, 1, 0, p;\n}\n"
                 : "=r"(ok) : "r"(bar), "r"(parity) : "memory");
    if (ok) return;
  }
  __trap();
}
__device__ __forceinline__ void mbar_wait_u(uint32_t bar, uint32_t parity) {
#pragma unroll 1
  for (uint32_t it = 0; it < (1u << 26); it++) {
    uint32_t ok;
    asm volatile("{\n.reg .pred p;\nmbarrier.try_wait.parity.shared::cta.b64 p, [%1], %2;\nselp.u32 %0, 1, 0, p;\n}\n"
                 : "=r"(ok) : "r"(bar), "r"(parity) : "memory");
    if (__all_sync(0xffffffffu, ok)) return;
  }
  __trap();
}
__device__ __forceinline__ void tma_2d(uint32_t dst, const CUtensorMap* tm, int c0, int c1, uint32_t bar) {
  asm volatile("cp.async.bulk.tensor.2d.shared::cluster.global.mbarrier::complete_tx::bytes [%0], [%1, {%3, %4}], [%2];\n"
               ::"r"(dst), "l"((uint64_t)tm), "r"(bar), "r"(c0), "r"(c1) : "memory");
}
__device__ __forceinline__ void cp_async16(uint32_t dst, const void* src) {
  asm volatile("cp.async.cg.shared.global [%0], [%1], 16;\n" ::"r"(dst), "l"(src) : "memory");
}
__device__ __forceinline__ void cp_async_arrive(uint32_t bar) {
  asm volatile("cp.async.mbarrier.arrive.noinc.shared::cta.b64 [%0];\n" ::"r"(bar) : "memory");
}
__device__ __forceinline__ void bulk_g2s(uint32_t dst, const void* src, uint32_t bytes, uint32_t bar) {
  asm volatile("cp.async.bulk.shared::cluster.global.mbarrier::complete_tx::bytes [%0], [%1], %2, [%3];\n"
               ::"r"(dst), "l"((uint64_t)src), "r"(bytes), "r"(bar) : "memory");
}
__device__ __forceinline__ void red_add_release(unsigned int* p) {
  asm volatile("fence.proxy.async.global;\nfence.acq_rel.gpu;\nred.relaxed.gpu.global.add.u32 [%0], 1;\n" ::"l"(p) : "memory");
}
__device__ __forceinline__ void tma_store_issue(const CUtensorMap* tm, uint32_t src, int c0, int c1) {
  asm volatile("cp.async.bulk.tensor.2d.global.shared::cta.bulk_group [%0, {%2, %3}], [%1];\n" ::"l"((uint64_t)tm), "r"(src), "r"(c0), "r"(c1) : "memory");
}
__device__ __forceinline__ void tma_store_2d(const CUtensorMap* tm, uint32_t src, int c0, int c1) {
  asm volatile("cp.async.bulk.tensor.2d.global.shared::cta.bulk_group [%0, {%2, %3}], [%1];\n" ::"l"((uint64_t)tm), "r"(src), "r"(c0), "r"(c1) : "memory");
  asm volatile("cp.async.bulk.commit_group;\ncp.async.bulk.wait_group.read 0;\n" ::: "memory");
}
__device__ __forceinline__ uint32_t ld_acquire(const unsigned int* p) {
  uint32_t v; asm volatile("ld.acquire.gpu.global.u32 %0, [%1];\n" : "=r"(v) : "l"(p) : "memory"); return v;
}
__device__ __forceinline__ void wait_counter(const unsigned int* p, uint32_t target) {
#pragma unroll 1
  for (uint32_t it = 0; it < (1u << 24); it++) {
    if ((int32_t)(ld_acquire(p) - target) >= 0) return;
  }
  __trap();
}
template <class F>
__device__ __forceinline__ void wait4_each(const unsigned int* p, uint32_t target, F f) {
  uint32_t done = 0;
#pragma unroll 1
  for (uint32_t it = 0; it < (1u << 24); it++) {
    uint32_t v[4];
    asm volatile("ld.acquire.gpu.global.v4.u32 {%0,%1,%2,%3}, [%4];\n" : "=r"(v[0]), "=r"(v[1]), "=r"(v[2]), "=r"(v[3]) : "l"(p) : "memory");
    uint32_t rdy = 0;
#pragma unroll
    for (int j = 0; j < 4; j++) rdy |= ((int32_t)(v[j] - target) >= 0) ? (1u << j) : 0u;
    rdy &= ~done;
    if (rdy) {
#pragma unroll
      for (int j = 0; j < 4; j++) if (rdy & (1u << j)) f(j);
      done |= rdy;
      if (done == 15u) return;
    }
  }
  __trap();
}
__device__ __forceinline__ void ldsm_x4(uint32_t (&r)[4], uint32_t addr) {
  asm volatile("ldmatrix.sync.aligned.m8n8.x4.shared.b16 {%0,%1,%2,%3}, [%4];\n" : "=r"(r[0]), "=r"(r[1]), "=r"(r[2]), "=r"(r[3]) : "r"(addr) : "memory");
}
__device__ __forceinline__ void ldsm_x4_t(uint32_t (&r)[4], uint32_t addr) {
  asm volatile("ldmatrix.sync.aligned.m8n8.x4.trans.shared.b16 {%0,%1,%2,%3}, [%4];\n" : "=r"(r[0]), "=r"(r[1]), "=r"(r[2]), "=r"(r[3]) : "r"(addr) : "memory");
}
__device__ __forceinline__ uint32_t pack_bf16(float lo, float hi) {
  uint32_t r; asm("cvt.rn.bf16x2.f32 %0, %1, %2;" : "=r"(r) : "f"(hi), "f"(lo)); return r;
}
__device__ __forceinline__ uint32_t pack_f16(float lo, float hi) {
  uint32_t r; asm("cvt.rn.f16x2.f32 %0, %1, %2;" : "=r"(r) : "f"(hi), "f"(lo)); return r;
}
__device__ __forceinline__ float bf_lo(uint32_t v) { return __uint_as_float(v << 16); }
__device__ __forceinline__ float bf_hi(uint32_t v) { return __uint_as_float(v & 0xFFFF0000u); }
__device__ __forceinline__ float bf16_round(float x) { return __bfloat162float(__float2bfloat16_rn(x)); }
__device__ __forceinline__ float ex2(float x) { float r; asm("ex2.approx.ftz.f32 %0, %1;" : "=f"(r) : "f"(x)); return r; }
__device__ __forceinline__ void sts32(uint32_t a, uint32_t v) { asm volatile("st.shared.b32 [%0], %1;\n" ::"r"(a), "r"(v) : "memory"); }
__device__ __forceinline__ void sts64(uint32_t a, uint32_t v0, uint32_t v1) { asm volatile("st.shared.v2.b32 [%0], {%1,%2};\n" ::"r"(a), "r"(v0), "r"(v1) : "memory"); }
__device__ __forceinline__ void sts128(uint32_t a, uint32_t v0, uint32_t v1, uint32_t v2, uint32_t v3) {
  asm volatile("st.shared.v4.b32 [%0], {%1,%2,%3,%4};\n" ::"r"(a), "r"(v0), "r"(v1), "r"(v2), "r"(v3) : "memory");
}
__device__ __forceinline__ uint32_t lds32(uint32_t a) { uint32_t v; asm volatile("ld.shared.b32 %0, [%1];\n" : "=r"(v) : "r"(a) : "memory"); return v; }
__device__ __forceinline__ float ldsf(uint32_t a) { float v; asm volatile("ld.shared.f32 %0, [%1];\n" : "=f"(v) : "r"(a) : "memory"); return v; }
__device__ __forceinline__ void lds128(uint32_t (&v)[4], uint32_t a) {
  asm volatile("ld.shared.v4.b32 {%0,%1,%2,%3}, [%4];\n" : "=r"(v[0]), "=r"(v[1]), "=r"(v[2]), "=r"(v[3]) : "r"(a) : "memory");
}

__device__ __forceinline__ float opaque_copy(float v) { float r; asm volatile("mov.f32 %0, %1;" : "=f"(r) : "f"(v)); return r; }

__device__ __forceinline__ void wgmma_qk64(float (&d)[32], const uint32_t (&a)[4], uint64_t db) {
  asm volatile(
      "wgmma.mma_async.sync.aligned.m64n64k16.f32.bf16.bf16 "
      "{%0,%1,%2,%3,%4,%5,%6,%7,%8,%9,%10,%11,%12,%13,%14,%15,%16,%17,%18,%19,%20,%21,%22,%23,%24,%25,%26,%27,%28,%29,%30,%31}, "
      "{%32,%33,%34,%35}, %36, 0, 1, 1, 0;\n"
      : "=f"(d[0]), "=f"(d[1]), "=f"(d[2]), "=f"(d[3]), "=f"(d[4]), "=f"(d[5]), "=f"(d[6]), "=f"(d[7]), "=f"(d[8]), "=f"(d[9]), "=f"(d[10]),
        "=f"(d[11]), "=f"(d[12]), "=f"(d[13]), "=f"(d[14]), "=f"(d[15]), "=f"(d[16]), "=f"(d[17]), "=f"(d[18]), "=f"(d[19]), "=f"(d[20]),
        "=f"(d[21]), "=f"(d[22]), "=f"(d[23]), "=f"(d[24]), "=f"(d[25]), "=f"(d[26]), "=f"(d[27]), "=f"(d[28]), "=f"(d[29]), "=f"(d[30]),
        "=f"(d[31])
      : "r"(a[0]), "r"(a[1]), "r"(a[2]), "r"(a[3]), "l"(db));
}
__device__ __forceinline__ void wgmma_rs24(float (&d)[12], const uint32_t (&a)[4], uint64_t db) {
  asm volatile("wgmma.mma_async.sync.aligned.m64n24k16.f32.bf16.bf16 {%0,%1,%2,%3,%4,%5,%6,%7,%8,%9,%10,%11}, {%12,%13,%14,%15}, %16, 1, 1, 1, 0;\n"
               : "+f"(d[0]), "+f"(d[1]), "+f"(d[2]), "+f"(d[3]), "+f"(d[4]), "+f"(d[5]), "+f"(d[6]), "+f"(d[7]), "+f"(d[8]), "+f"(d[9]),
                 "+f"(d[10]), "+f"(d[11])
               : "r"(a[0]), "r"(a[1]), "r"(a[2]), "r"(a[3]), "l"(db));
}
__device__ __forceinline__ void wgmma_ss8_tb(float (&d)[4], uint64_t da, uint64_t db) {
  asm volatile("wgmma.mma_async.sync.aligned.m64n8k16.f32.bf16.bf16 {%0,%1,%2,%3}, %4, %5, 1, 1, 1, 0, 1;\n"
               : "+f"(d[0]), "+f"(d[1]), "+f"(d[2]), "+f"(d[3]) : "l"(da), "l"(db));
}
__device__ __forceinline__ void wgmma_ss32(float (&d)[16], uint64_t da, uint64_t db) {
  asm volatile(
      "wgmma.mma_async.sync.aligned.m64n32k16.f32.bf16.bf16 {%0,%1,%2,%3,%4,%5,%6,%7,%8,%9,%10,%11,%12,%13,%14,%15}, %16, %17, 1, 1, 1, 0, 0;\n"
      : "+f"(d[0]), "+f"(d[1]), "+f"(d[2]), "+f"(d[3]), "+f"(d[4]), "+f"(d[5]), "+f"(d[6]), "+f"(d[7]), "+f"(d[8]), "+f"(d[9]), "+f"(d[10]),
        "+f"(d[11]), "+f"(d[12]), "+f"(d[13]), "+f"(d[14]), "+f"(d[15])
      : "l"(da), "l"(db));
}
__device__ __forceinline__ void wgmma_ss24_ta(float (&d)[12], uint64_t da, uint64_t db) {
  asm volatile("wgmma.mma_async.sync.aligned.m64n24k16.f32.bf16.bf16 {%0,%1,%2,%3,%4,%5,%6,%7,%8,%9,%10,%11}, %12, %13, 1, 1, 1, 1, 0;\n"
               : "+f"(d[0]), "+f"(d[1]), "+f"(d[2]), "+f"(d[3]), "+f"(d[4]), "+f"(d[5]), "+f"(d[6]), "+f"(d[7]), "+f"(d[8]), "+f"(d[9]),
                 "+f"(d[10]), "+f"(d[11])
               : "l"(da), "l"(db));
}
__device__ __forceinline__ void wgmma_ss16_ta(float (&d)[8], uint64_t da, uint64_t db) {
  asm volatile("wgmma.mma_async.sync.aligned.m64n16k16.f32.bf16.bf16 {%0,%1,%2,%3,%4,%5,%6,%7}, %8, %9, 1, 1, 1, 1, 0;\n"
               : "+f"(d[0]), "+f"(d[1]), "+f"(d[2]), "+f"(d[3]), "+f"(d[4]), "+f"(d[5]), "+f"(d[6]), "+f"(d[7])
               : "l"(da), "l"(db));
}
__device__ __forceinline__ void wgmma_ss16_f16(float (&d)[8], uint64_t da, uint64_t db) {
  asm volatile("wgmma.mma_async.sync.aligned.m64n16k16.f32.f16.f16 {%0,%1,%2,%3,%4,%5,%6,%7}, %8, %9, 1, 1, 1, 0, 0;\n"
               : "+f"(d[0]), "+f"(d[1]), "+f"(d[2]), "+f"(d[3]), "+f"(d[4]), "+f"(d[5]), "+f"(d[6]), "+f"(d[7])
               : "l"(da), "l"(db));
}

__device__ __forceinline__ uint32_t exp_pair_mufu(float x0, float x1) { return pack_bf16(ex2(x0), ex2(x1)); }
__device__ __forceinline__ uint32_t exp_pair_poly(float x0, float x1, uint32_t c1, uint32_t c2) {
  const float M0 = 98430.3984375f, M1 = 98286.8984375f;
  uint32_t y, t, e, p;
  float r0 = x0 + M0, r1 = x1 + M1;
  asm("mad.lo.u32 %0, %1, 65536, %2;" : "=r"(y) : "r"(__float_as_uint(r1)), "r"(__float_as_uint(r0)));
  asm("lop3.b32 %0, %1, 0x007F007F, %2, 0xEA;" : "=r"(t) : "r"(y), "r"(c1));
  asm("lop3.b32 %0, %1, 0xFF80FF80, %2, 0xEA;" : "=r"(e) : "r"(y), "r"(c2));
  asm("fma.rn.bf16x2 %0, %1, %2, %3;" : "=r"(p) : "r"(y), "r"(t), "r"(e));
  return p;
}
__host__ __device__ constexpr bool is_poly(int i) { return ((i + 1) * 10) / 16 != (i * 10) / 16; }

__device__ __forceinline__ void wgmma_ss128_tb(float (&d)[64], uint64_t da, uint64_t db) {
  asm volatile("wgmma.mma_async.sync.aligned.m64n128k16.f32.bf16.bf16 {%0, %1, %2, %3, %4, %5, %6, %7, %8, %9, %10, %11, %12, %13, %14, %15, %16, %17, %18, %19, %20, %21, %22, %23, %24, %25, %26, %27, %28, %29, %30, %31, %32, %33, %34, %35, %36, %37, %38, %39, %40, %41, %42, %43, %44, %45, %46, %47, %48, %49, %50, %51, %52, %53, %54, %55, %56, %57, %58, %59, %60, %61, %62, %63}, %64, %65, 1, 1, 1, 0, 1;\n"
               : "+f"(d[0]), "+f"(d[1]), "+f"(d[2]), "+f"(d[3]), "+f"(d[4]), "+f"(d[5]), "+f"(d[6]), "+f"(d[7]), "+f"(d[8]), "+f"(d[9]), "+f"(d[10]), "+f"(d[11]), "+f"(d[12]), "+f"(d[13]), "+f"(d[14]), "+f"(d[15]), "+f"(d[16]), "+f"(d[17]), "+f"(d[18]), "+f"(d[19]), "+f"(d[20]), "+f"(d[21]), "+f"(d[22]), "+f"(d[23]), "+f"(d[24]), "+f"(d[25]), "+f"(d[26]), "+f"(d[27]), "+f"(d[28]), "+f"(d[29]), "+f"(d[30]), "+f"(d[31]), "+f"(d[32]), "+f"(d[33]), "+f"(d[34]), "+f"(d[35]), "+f"(d[36]), "+f"(d[37]), "+f"(d[38]), "+f"(d[39]), "+f"(d[40]), "+f"(d[41]), "+f"(d[42]), "+f"(d[43]), "+f"(d[44]), "+f"(d[45]), "+f"(d[46]), "+f"(d[47]), "+f"(d[48]), "+f"(d[49]), "+f"(d[50]), "+f"(d[51]), "+f"(d[52]), "+f"(d[53]), "+f"(d[54]), "+f"(d[55]), "+f"(d[56]), "+f"(d[57]), "+f"(d[58]), "+f"(d[59]), "+f"(d[60]), "+f"(d[61]), "+f"(d[62]), "+f"(d[63])
               : "l"(da), "l"(db));
}

__device__ __forceinline__ void load_kv_chunk(uint32_t sb, int c) {
  const uint32_t bar = sb + SM_BAR + 8 * (MB_KV0 + c);
  const uint32_t v0 = c == 0 ? 0 : c * 8704 + 144, vn = c == 0 ? 8848 : 8704;
  mbar_expect_tx(bar, c == 0 ? 8192 + 8848 + 2048 : 8192 + 8704);
  bulk_g2s(sb + SM_K + c * 8192, g_Kimg + c * 8192, 8192, bar);
  bulk_g2s(sb + SM_V + v0, g_Vimg + v0, vn, bar);
  if (c == 0) bulk_g2s(sb + SM_STAT, g_stat, 2048, bar);
}
__device__ __forceinline__ void kv_step(uint32_t sb, int jo) {
  mbar_wait_u(sb + SM_BAR + 8 * (MB_KV0 + jo), 0);
  if (jo < 6 && threadIdx.x == ((jo & 3) << 7)) load_kv_chunk(sb, jo + 2);
  __syncwarp();
}

template <bool FAST>
__device__ __forceinline__ void attn_tile(float (&o)[12], const uint32_t (&q)[4], uint32_t sb, bool first, float m0, float m1) {
  constexpr uint64_t dvs = 34;
  uint64_t dk = make_desc(sb + SM_K, 128, 256, 0);
  uint64_t dv = make_desc(sb + SM_V, 272, 144, 0);
  uint32_t c1 = 0x3F003F00u, c2 = 0x00030003u;
  asm volatile("" : "+r"(c1), "+r"(c2));
#pragma unroll
  for (int i = 0; i < 12; i++) o[i] = 0.f;
  fence_regs(o);
  constexpr int kUnroll = FAST ? 4 : 1;
#pragma unroll 1
  for (int jo = 0; jo < 8; jo++) {
    if (first) kv_step(sb, jo);
#pragma unroll kUnroll
    for (int ji = 0; ji < 4; ji++) {
      float s[32];
      uint32_t p[4][4];
      wg_fence();
      wgmma_qk64(s, q, dk);
      dk += 128;
      wg_commit();
      wg_wait<0>();
      fence_regs(s);
      fence_regs(o);
#pragma unroll
      for (int b = 0; b < 4; b++)
#pragma unroll
        for (int i = 0; i < 4; i++) {
          const float x0 = s[8 * b + 2 * i], x1 = s[8 * b + 2 * i + 1];
          if (FAST) {
            p[b][i] = is_poly(b * 4 + i) ? exp_pair_poly(x0, x1, c1, c2) : exp_pair_mufu(x0, x1);
          } else {
            const float m = (i & 1) ? m1 : m0;
            p[b][i] = exp_pair_mufu(x0 - m, x1 - m);
          }
        }
      wg_fence();
#pragma unroll
      for (int b = 0; b < 4; b++) { wgmma_rs24(o, p[b], dv); dv += dvs; }
      wg_commit();
      if (!FAST) { wg_wait<0>(); fence_regs(o); }
    }
  }
  wg_wait<0>();
  fence_regs(o);
}
__device__ __forceinline__ void attn_rowmax(const uint32_t (&q)[4], uint32_t sb, bool first, float& m0, float& m1) {
  const uint64_t dk0 = make_desc(sb + SM_K, 128, 256, 0);
  float a0 = -INFINITY, a1 = -INFINITY;
#pragma unroll 1
  for (int j = 0; j < 32; j++) {
    if (first && (j & 3) == 0) kv_step(sb, j >> 2);
    float s[32];
    wg_fence();
    wgmma_qk64(s, q, dk0 + (uint64_t)(j * 128));
    wg_commit();
    wg_wait<0>();
    fence_regs(s);
#pragma unroll
    for (int i = 0; i < 8; i++) {
      a0 = fmaxf(a0, fmaxf(s[4 * i], s[4 * i + 1]));
      a1 = fmaxf(a1, fmaxf(s[4 * i + 2], s[4 * i + 3]));
    }
  }
  a0 = fmaxf(a0, __shfl_xor_sync(~0u, a0, 1)); a0 = fmaxf(a0, __shfl_xor_sync(~0u, a0, 2));
  a1 = fmaxf(a1, __shfl_xor_sync(~0u, a1, 1)); a1 = fmaxf(a1, __shfl_xor_sync(~0u, a1, 2));
  m0 = a0; m1 = a1;
}

struct cplx { float r, i; };
__device__ __forceinline__ cplx cmul(cplx a, cplx b) { return {fmaf(a.r, b.r, -a.i * b.i), fmaf(a.r, b.i, a.i * b.r)}; }
__device__ __forceinline__ cplx cexp_pos(float ar, float ai, float p) {
  float mag = ex2(ar * p * 1.4426950408889634f);
  float th = ai * p;
  float k = rintf(th * 0.15915494309189535f);
  float tr = fmaf(-k, 6.2831854820251465f, th);
  tr = fmaf(-k, -1.7484555e-7f, tr);
  return {mag * __cosf(tr), mag * __sinf(tr)};
}
__device__ __forceinline__ uint32_t swz64(uint32_t a) { return a ^ ((a >> 3) & 0x30u); }
__device__ __forceinline__ uint32_t u_addr(uint32_t base, int ip) { return swz64(base + 2 * ip); }

__device__ __forceinline__ cplx csqr(cplx a) { return {fmaf(a.r, a.r, -a.i * a.i), 2.f * a.r * a.i}; }
constexpr int SSM_BAR = 5;

__device__ __forceinline__ void ssm_kgen_all(const Params& P, int b, uint32_t sb, int tid, int w) {
  const uint32_t ss = sb + SM_JOB;
  const int lane = tid & 31;
  const uint32_t ta = ss + SS_TA + (tid >> 2) * 144 + (tid & 3) * 4;
  const uint32_t tb = ss + SS_TB + (tid >> 2) * 144 + (tid & 3) * 4;
  const uint32_t sred = sb + SM_RED;
  uint32_t raw[4][2];
  float ldt[4];
#pragma unroll
  for (int ch = 0; ch < 4; ch++) {
    const int i = (4 * b + ch) * 128 + tid;
    raw[ch][0] = (uint32_t)__bfloat16_as_ushort(P.log_A_real[i]) | ((uint32_t)__bfloat16_as_ushort(P.A_imag[i]) << 16);
    raw[ch][1] = (uint32_t)__bfloat16_as_ushort(P.C_real[i]) | ((uint32_t)__bfloat16_as_ushort(P.C_imag[i]) << 16);
    ldt[ch] = __bfloat162float(P.log_dt[4 * b + ch]);
  }
  auto put = [&](int h, cplx v) { sts32(ta + (h >> 3) * 4608 + (h & 7) * 16, pack_f16(v.r, v.i)); };
#pragma unroll 1
  for (int ch = 0; ch < 4; ch++) {
    const uint32_t r0 = ch == 0 ? raw[0][0] : (ch == 1 ? raw[1][0] : (ch == 2 ? raw[2][0] : raw[3][0]));
    const uint32_t r1 = ch == 0 ? raw[0][1] : (ch == 1 ? raw[1][1] : (ch == 2 ? raw[2][1] : raw[3][1]));
    const float dt = bf16_round(expf(ch == 0 ? ldt[0] : (ch == 1 ? ldt[1] : (ch == 2 ? ldt[2] : ldt[3]))));
    const float ar = -bf16_round(expf(bf_lo(r0))) * dt, ai = bf_hi(r0) * dt;
    const float Cr = 2.f * (bf_lo(r1) * dt), Ci = 2.f * (bf_hi(r1) * dt);
    const uint32_t wmx = __reduce_max_sync(~0u, __float_as_uint(fmaxf(fabsf(Cr), fabsf(Ci))));
    if (lane == 0) sts32(sred + ch * 16 + w * 4, wmx);
    const cplx w64 = cexp_pos(ar, ai, 64.f), w8 = cexp_pos(ar, ai, 8.f), w1024 = cexp_pos(ar, ai, 1024.f);
    const cplx w128 = csqr(w64);
    cplx z[8];
    z[1] = cexp_pos(ar, ai, 1.f);
    z[2] = csqr(z[1]);
    z[4] = csqr(z[2]);
    z[3] = cmul(z[1], z[2]); z[5] = cmul(z[4], z[1]); z[6] = cmul(z[4], z[2]); z[7] = cmul(z[4], z[3]);
    if (ch == 0) mbar_wait_u(sb + SM_BAR + 8 * MB_QDONE, 0);
    bar_sync(SSM_BAR, 128);
    uint32_t mxv[4];
    lds128(mxv, sred + ch * 16);
    uint32_t eb = (max(max(mxv[0], mxv[1]), max(mxv[2], mxv[3])) >> 23) & 0xFF;
    eb = eb < 2 ? 2 : (eb > 252 ? 252 : eb);
    const float sc = __uint_as_float((eb + 1) << 23);
    const float isc = __uint_as_float((253 - eb) << 23);
    cplx G = {Cr * isc, Ci * isc};
    cplx G8 = cmul(G, w1024);
    const cplx w8c = {w8.r, -w8.i};
    cplx x = {1.f, 0.f}, y = {w64.r, -w64.i};
#pragma unroll
    for (int g = 0; g < 8; g++) {
      sts32(tb + g * 16, pack_f16(x.r, x.i));
      sts32(tb + 4608 + g * 16, pack_f16(y.r, y.i));
      if (g < 7) { x = (g == 0) ? w8c : cmul(x, w8c); y = cmul(y, w8c); }
      put(32 + g, G8);
      G8 = cmul(G8, w128);
      if (g < 2) {
        put(g * 8, G);
#pragma unroll
        for (int r = 1; r < 8; r++) put(g * 8 + r, cmul(G, z[r]));
      } else if (g < 4) {
        put(16 + (g - 2) * 4, G);
#pragma unroll
        for (int r = 1; r < 4; r++) put(16 + (g - 2) * 4 + r, cmul(G, z[2 * r]));
      } else {
        put(24 + (g - 4) * 2, G);
        put(24 + (g - 4) * 2 + 1, cmul(G, z[4]));
      }
      if (g < 7) G = cmul(G, w128);
    }
    put(40, G8);
    fence_async_smem();
    bar_sync(SSM_BAR, 128);
    float acc[8];
#pragma unroll
    for (int i = 0; i < 8; i++) acc[i] = 0.f;
    fence_regs(acc);
    const uint64_t da0 = make_desc(ss + SS_TA, 144, 4608, 0), db0 = make_desc(ss + SS_TB, 144, 4608, 0);
    wg_fence();
#pragma unroll
    for (int ks = 0; ks < 16; ks++) wgmma_ss16_f16(acc, da0 + (uint64_t)(ks * 18), db0 + (uint64_t)(ks * 18));
    wg_commit();
    wg_wait<0>();
    fence_regs(acc);
    const uint32_t sT = sb + SM_T + ch * 3136;
    if (w < 3) {
      const uint32_t t0 = sT + ((16 * w + (lane >> 2)) * 16 + 2 * (lane & 3)) * 4;
      sts64(t0, __float_as_uint(acc[0] * sc), __float_as_uint(acc[1] * sc));
      sts64(t0 + 512, __float_as_uint(acc[2] * sc), __float_as_uint(acc[3] * sc));
      sts64(t0 + 32, __float_as_uint(acc[4] * sc), __float_as_uint(acc[5] * sc));
      sts64(t0 + 512 + 32, __float_as_uint(acc[6] * sc), __float_as_uint(acc[7] * sc));
    } else if (lane == 0) {
      sts32(sT + 3072, 0u);
    }
  }
}

__device__ __forceinline__ void ssm_conv(const Params& P, int d, uint32_t sb, uint32_t su, uint32_t sT, int tid, int w) {
  const uint32_t ss = sb + SM_JOB;
  const int lane = tid & 31;
  const float k256 = ldsf(sT + 16 * 64), k1024 = ldsf(sT + 32 * 64);
  if (tid < 126) {
    const uint4 h0 = __ldg((const uint4*)&g_hidx.v[tid * 16]), h1 = __ldg((const uint4*)&g_hidx.v[tid * 16 + 8]);
    const uint32_t hx[8] = {h0.x, h0.y, h0.z, h0.w, h1.x, h1.y, h1.z, h1.w};
    float g[15];
#pragma unroll
    for (int e = 0; e < 15; e++) g[e] = ldsf(sT + ((e & 1) ? (hx[e >> 1] >> 16) : (hx[e >> 1] & 0xFFFFu)));
    if (tid == 4) g[0] -= k256;
    if (tid == 3) g[8] -= k256;
    uint32_t pe[7], po[7];
#pragma unroll
    for (int k = 0; k < 7; k++) { pe[k] = pack_bf16(g[2 * k], g[2 * k + 1]); po[k] = pack_bf16(g[2 * k + 1], g[2 * k + 2]); }
    const uint32_t hb = ss + SS_H + tid * 144;
#pragma unroll
    for (int r = 0; r < 4; r++) {
      sts128(hb + r * 32, pe[r], pe[r + 1], pe[r + 2], pe[r + 3]);
      sts128(hb + r * 32 + 16, po[r], po[r + 1], po[r + 2], po[r + 3]);
    }
  }
  {
    const int tau = (tid == 127) ? -1 : tid;
    if (tau < 112) {
      float v[32];
#pragma unroll
      for (int c = 0; c < 4; c++) {
        uint32_t w4[4];
        lds128(w4, u_addr(su, 16 * tau - 8 + 256 + 8 * c));
#pragma unroll
        for (int i = 0; i < 4; i++) { v[8 * c + 2 * i] = bf_lo(w4[i]); v[8 * c + 2 * i + 1] = bf_hi(w4[i]); }
      }
      float s[16];
#pragma unroll
      for (int i = 0; i < 16; i++) s[i] = v[7 + i] + v[8 + i] + v[9 + i];
#pragma unroll
      for (int r = 0; r < 4; r++) {
        const uint32_t xa = swz64(ss + SS_X1E + 8 * tau + 128) + r * 1024;
        sts64(xa, pack_bf16(s[r], s[4 + r]), pack_bf16(s[8 + r], s[12 + r]));
        sts64(xa + (SS_X1O - SS_X1E), pack_bf16(v[6 + r], v[10 + r]), pack_bf16(v[14 + r], v[18 + r]));
      }
      if (tau < 99) {
#pragma unroll
        for (int c = 0; c < 4; c++)
          sts64(ss + SS_Y2O + (16 * tau + 4 * c + 4 + 512) * 2, pack_bf16(s[4 * c], s[4 * c + 1]), pack_bf16(s[4 * c + 2], s[4 * c + 3]));
#pragma unroll
        for (int i = 0; i < 16; i++) s[i] += v[6 + i] + v[10 + i];
#pragma unroll
        for (int c = 0; c < 2; c++)
          sts128(ss + SS_Y2E + (16 * tau + 8 * c + 8 + 512) * 2, pack_bf16(s[8 * c], s[8 * c + 1]), pack_bf16(s[8 * c + 2], s[8 * c + 3]),
                 pack_bf16(s[8 * c + 4], s[8 * c + 5]), pack_bf16(s[8 * c + 6], s[8 * c + 7]));
        if (tau < 64) {
#pragma unroll
          for (int i = 0; i < 16; i++) s[i] += v[5 + i] + v[11 + i];
          const int i0 = tau + 64, i1 = tau + 65;
          const uint32_t r0 = (i0 >> 4) * 512 + (i0 & 15) * 16, r1 = (i1 >> 4) * 512 + (i1 & 15) * 16;
          sts128(ss + SS_Y3O + 256 + r0, pack_bf16(s[0], s[1]), pack_bf16(s[2], s[3]), pack_bf16(s[4], s[5]), pack_bf16(s[6], s[7]));
          if (tau < 63) {
            sts128(ss + SS_Y3O + r1, pack_bf16(s[8], s[9]), pack_bf16(s[10], s[11]), pack_bf16(s[12], s[13]), pack_bf16(s[14], s[15]));
#pragma unroll
            for (int i = 0; i < 16; i++) s[i] += v[4 + i] + v[12 + i];
            sts128(ss + SS_Y3E + r1, pack_bf16(s[0], s[1]), pack_bf16(s[2], s[3]), pack_bf16(s[4], s[5]), pack_bf16(s[6], s[7]));
            sts128(ss + SS_Y3E + 256 + r1, pack_bf16(s[8], s[9]), pack_bf16(s[10], s[11]), pack_bf16(s[12], s[13]), pack_bf16(s[14], s[15]));
          }
        }
      }
    }
    if (tid >= 64 && tid < 127) {
      const int z = tid - 64;
      if (z < 60) { const uint32_t xa = swz64(ss + SS_X1E + (z % 15) * 8) + (z / 15) * 1024; sts64(xa, 0, 0); sts64(xa + (SS_X1O - SS_X1E), 0, 0); }
      sts128(ss + SS_Y2E + z * 16, 0, 0, 0, 0);
      if (z < 62) sts128(ss + SS_Y2O + z * 16, 0, 0, 0, 0);
      if (z == 62) sts64(ss + SS_Y2O + 992, 0, 0);
      if (z < 3) sts64(ss + SS_Y2O + (1588 + 512) * 2 + z * 8, 0, 0);
      if (z == 3) sts128(ss + SS_Y2E + (1592 + 512) * 2, 0, 0, 0, 0);
      sts128(ss + SS_Y3O + z * 16, 0, 0, 0, 0);
      sts128(ss + SS_Y3O + 1024 + z * 16, 0, 0, 0, 0);
      sts128(ss + SS_Y3E + z * 16, 0, 0, 0, 0);
      sts128(ss + SS_Y3E + 1024 + z * 16, 0, 0, 0, 0);
      if (z == 4) { sts128(ss + SS_Y3O + 63 * 16, 0, 0, 0, 0); sts128(ss + SS_Y3E + 63 * 16, 0, 0, 0, 0); sts128(ss + SS_Y3E + 1024 + 63 * 16, 0, 0, 0, 0); }
    }
  }
  fence_async_smem();
  bar_sync(SSM_BAR, 128);
  float a0[16], a1[16], a2[12], a3[8];
  {
    const uint64_t dh = make_desc(ss + SS_H, 144, 144, 0);
    const uint64_t d0 = make_desc(su, 16, 512, 2);
    const uint64_t d1 = make_desc(ss + SS_X1E, 16, 512, 2);
    const uint64_t d2 = make_desc(ss + SS_Y2E, 128, 384, 0);
    const uint64_t d3 = make_desc(ss + SS_Y3E, 128, 256, 0);
#pragma unroll
    for (int i = 0; i < 16; i++) { a0[i] = 0.f; a1[i] = 0.f; }
#pragma unroll
    for (int i = 0; i < 12; i++) a2[i] = 0.f;
#pragma unroll
    for (int i = 0; i < 8; i++) a3[i] = 0.f;
    fence_regs(a0); fence_regs(a1); fence_regs(a2); fence_regs(a3);
    wg_fence();
#pragma unroll
    for (int k = 0; k < 18; k++) wgmma_ss32(a0, d0 + (uint64_t)(k * 2), dh + (uint64_t)(k * 18));
#pragma unroll
    for (int j = 0; j < 12; j++)
      wgmma_ss32(a1, d1 + (uint64_t)((j / 6) * ((SS_X1O - SS_X1E) / 16) + (j % 6) * 2), dh + (uint64_t)(((j / 6) ? 56 : 40) * 9 + (j % 6) * 18));
#pragma unroll
    for (int j = 0; j < 12; j++)
      wgmma_ss24_ta(a2, d2 + (uint64_t)((j / 6) * ((SS_Y2O - SS_Y2E) / 16) + (j % 6) * 16), dh + (uint64_t)(((j / 6) ? 87 : 72) * 9 + (j % 6) * 18));
#pragma unroll
    for (int j = 0; j < 10; j++)
      wgmma_ss16_ta(a3, d3 + (uint64_t)((j / 5) * ((SS_Y3O - SS_Y3E) / 16) + (j % 5) * 32), dh + (uint64_t)(((j / 5) ? 114 : 102) * 9 + (j % 5) * 18));
    wg_commit();
    wg_wait<0>();
    fence_regs(a0); fence_regs(a1); fence_regs(a2); fence_regs(a3);
  }
  bar_sync(SSM_BAR, 128);
  {
    const int rq = lane >> 2, q2 = 2 * (lane & 3);
#pragma unroll
    for (int hh = 0; hh < 2; hh++) {
      const int row = 16 * w + rq + 8 * hh;
#pragma unroll
      for (int i = 0; i < 4; i++) {
        int l = 32 * row + 30 - 8 * i - q2;
        sts64(ss + SS_Y0 + l * 4, __float_as_uint(a0[4 * i + 2 * hh + 1]), __float_as_uint(a0[4 * i + 2 * hh]));
      }
      if ((row & 15) < 14) {
        const uint32_t bb = ss + SS_Y1 + (4 * (32 * (row & 15) + 31 - q2) + (row >> 4)) * 4;
#pragma unroll
        for (int i = 0; i < 4; i++)
#pragma unroll
          for (int e = 0; e < 2; e++) sts32(bb - (8 * i + e) * 16, __float_as_uint(a1[4 * i + 2 * hh + e]));
      }
      {
        const uint32_t bb = ss + SS_Y2 + (8 * (24 * (row >> 3) + 23 - q2) + (row & 7)) * 4;
#pragma unroll
        for (int i = 0; i < 3; i++)
#pragma unroll
          for (int e = 0; e < 2; e++) sts32(bb - (8 * i + e) * 32, __float_as_uint(a2[4 * i + 2 * hh + e]));
      }
      {
        const uint32_t bb = ss + SS_Y3 + (16 * (16 * (row >> 4) + 15 - q2) + (row & 15)) * 4;
#pragma unroll
        for (int i = 0; i < 2; i++)
#pragma unroll
          for (int e = 0; e < 2; e++) sts32(bb - (8 * i + e) * 64, __float_as_uint(a3[4 * i + 2 * hh + e]));
      }
    }
  }
  const uint32_t dsk2 = (uint32_t)__bfloat16_as_ushort(P.D_skip[d]) * 0x10001u;
  bar_sync(SSM_BAR, 128);
#pragma unroll
  for (int j = 0; j < 4; j++) {
    const int l = 4 * (tid + 128 * j);
    uint32_t t[4];
    float y[4];
    lds128(t, ss + SS_Y0 + l * 4);
#pragma unroll
    for (int i = 0; i < 4; i++) y[i] = __uint_as_float(t[i]);
    if (j > 0 || tid >= 64) {
      lds128(t, ss + SS_Y1 + (l - 256) * 4);
#pragma unroll
      for (int i = 0; i < 4; i++) y[i] += __uint_as_float(t[i]);
    }
    if (j > 0) {
      lds128(t, ss + SS_Y2 + (l - 512) * 4);
#pragma unroll
      for (int i = 0; i < 4; i++) y[i] += __uint_as_float(t[i]);
    }
    if (j > 1) {
      lds128(t, ss + SS_Y3 + (l - 1024) * 4);
      const uint32_t c0 = lds32(u_addr(su, l - 1032 + 256) + 4), c1 = lds32(u_addr(su, l - 1028 + 256)), c2 = lds32(u_addr(su, l - 1028 + 256) + 4);
      y[0] = fmaf(-k1024, bf_hi(c0), y[0] + __uint_as_float(t[0]));
      y[1] = fmaf(-k1024, bf_lo(c1), y[1] + __uint_as_float(t[1]));
      y[2] = fmaf(-k1024, bf_hi(c1), y[2] + __uint_as_float(t[2]));
      y[3] = fmaf(-k1024, bf_lo(c2), y[3] + __uint_as_float(t[3]));
    }
    if (j == 0 && tid == 63) y[3] = fmaf(k256, bf_lo(lds32(u_addr(su, 256))), y[3]);
    const uint32_t ua = u_addr(su, l + 256);
    const uint32_t w0 = lds32(ua), w1 = lds32(ua + 4);
    uint32_t o0, o1;
    asm("{\n.reg .b32 t;\nmul.rn.bf16x2 t, %1, %2;\nadd.rn.bf16x2 %0, %3, t;\n}\n" : "=r"(o0) : "r"(w0), "r"(dsk2), "r"(pack_bf16(y[0], y[1])));
    asm("{\n.reg .b32 t;\nmul.rn.bf16x2 t, %1, %2;\nadd.rn.bf16x2 %0, %3, t;\n}\n" : "=r"(o1) : "r"(w1), "r"(dsk2), "r"(pack_bf16(y[2], y[3])));
    *(uint2*)(g_Y + (size_t)d * 2048 + l) = make_uint2(o0, o1);
  }
  bar_sync(SSM_BAR, 128);
}

__global__ void __launch_bounds__(NTHREADS, 1)
fused_kernel(const __grid_constant__ CUtensorMap tm_wq, const __grid_constant__ CUtensorMap tm_wo,
             const __grid_constant__ CUtensorMap tm_out, const __grid_constant__ CUtensorMap tm_outb,
             const __grid_constant__ CUtensorMap tm_u, const Params P) {
  extern __shared__ __align__(1024) unsigned char smem[];
  const uint32_t sb = smem_u32(smem);
  const int tid_all = threadIdx.x;
  const int wg = __shfl_sync(0xffffffffu, (int)(threadIdx.x >> 7), 0);
  const int b = blockIdx.x, qb = b >> 2, hg = b & 3;
  const uint32_t bars = sb + SM_BAR;
  if (tid_all < NCOMP) {
    const int c = tid_all & 63, r0 = tid_all >> 6;
    const __nv_bfloat16* src = P.x + (size_t)(qb * 64 + r0) * DM + c * 8;
    const uint32_t dst = sb + SM_X + (c >> 3) * 8192 + r0 * 128 + (((c & 7) ^ r0) << 4);
#pragma unroll
    for (int i = 0; i < 8; i++) cp_async16(dst + i * 1024, src + (size_t)i * 8 * DM);
    cp_async16(sb + SM_WKV + tid_all * 16, ((hg < 2) ? P.wk : P.wv) + tid_all * 16 + (hg & 1) * 8);
  } else if (tid_all - NCOMP < MB_COUNT) {
    const int i = tid_all - NCOMP;
    uint32_t cnt = 1;
    if (i == MB_KVG || i == MB_ATT) cnt = 4;
    if (i == MB_EARLY) cnt = 16;
    if (i == MB_X || (i >= MB_WQ && i < MB_WQ + 7)) cnt = NCOMP;
    mbar_init(bars + 8 * i, cnt);
    asm volatile("fence.mbarrier_init.release.cluster;\n" ::: "memory");
    fence_async_smem();
  } else if (tid_all == NCOMP + 64) {
    asm volatile("prefetch.tensormap [%0];\n" ::"l"((uint64_t)&tm_wq) : "memory");
    asm volatile("prefetch.tensormap [%0];\n" ::"l"((uint64_t)&tm_u) : "memory");
    asm volatile("prefetch.tensormap [%0];\n" ::"l"((uint64_t)&tm_out) : "memory");
    asm volatile("prefetch.tensormap [%0];\n" ::"l"((uint64_t)&tm_outb) : "memory");
    asm volatile("prefetch.tensormap [%0];\n" ::"l"((uint64_t)&tm_wo) : "memory");
  }
  __syncthreads();
  if (tid_all < NCOMP) cp_async_arrive(bars + 8 * MB_X);
  if (wg >= 1) {
    const int t2 = tid_all - 128;
    const int c = t2 & 15, k = t2 >> 4;
    const __nv_bfloat16* src = P.wq + (size_t)k * DM + hg * 128 + c * 8;
    const uint32_t off = (c >> 3) * 8192 + k * 128 + (((c & 7) ^ (k & 7)) << 4);
#pragma unroll
    for (int pc = 0; pc < 7; pc++) {
      const uint32_t dst = sb + (pc < 4 ? SM_RING + pc * 16384 : (pc == 4 ? SM_WQ4 : SM_JOB + (pc - 5) * 16384)) + off;
      cp_async16(dst, src + (size_t)(pc * 64) * DM);
      cp_async16(dst + 4096, src + (size_t)(pc * 64 + 32) * DM);
      cp_async_arrive(bars + 8 * (MB_WQ + pc));
    }
  }
  const int tid = tid_all & 127, lane = tid & 31, w = __shfl_sync(0xffffffffu, tid >> 5, 0);
  const int rq = lane >> 2, q2 = 2 * (lane & 3);

  if (wg == 4) {
    uint32_t epoch = 0;
    if (tid == 0) epoch = *(volatile unsigned int*)&g_epoch[b];
    ssm_kgen_all(P, b, sb, tid, w);
    if (w == 0) {
      if (lane == 0) {
        mbar_wait(bars + 8 * MB_UFREE, 0);
        mbar_expect_tx(bars + 8 * MB_USTG, 16384);
        wait4_each(&g_uflag[qb * 4], epoch + 1, [](int) {});
      }
      __syncwarp();
      if (lane < 4) bulk_g2s(sb + SM_U + lane * U_STRIDE + 512, g_U + (size_t)(4 * b + lane) * 2048, 4096, bars + 8 * MB_USTG);
    }
    bar_sync(SSM_BAR, 128);
    mbar_wait_u(bars + 8 * MB_USTG, 0);
#pragma unroll 1
    for (int ch = 0; ch < 4; ch++) {
      ssm_conv(P, 4 * b + ch, sb, sb + SM_U + ch * U_STRIDE, sb + SM_T + ch * 3136, tid, w);
    }
    if (tid == 0) {
      const uint32_t rb = sb + SM_JOB;
      auto load_w = [&](uint32_t dst, int kb, uint32_t bar) {
        tma_2d(dst, &tm_wo, hg * 128, kb * 64, bar);
        tma_2d(dst + 8192, &tm_wo, hg * 128 + 64, kb * 64, bar);
      };
      const unsigned char* oimg = g_Oimg + qb * 65536;
      mbar_wait(bars + 8 * MB_EARLY, 0);
      red_add_release(&g_yflag[b]);
      asm volatile("red.relaxed.gpu.global.add.u32 [%0], 4;\n" ::"l"(&g_oflag[0][b]) : "memory");
      fence_async_smem();
      mbar_expect_tx(bars + 8 * MB_OA, 3 * 24576);
      for (int j = 0; j < 3; j++) load_w(rb + j * 16384, 2 * j, bars + 8 * MB_OA);
      wait4_each(&g_oflag[0][qb * 4], (epoch + 1) * 4, [](int) {});
      for (int j = 0; j < 3; j++) bulk_g2s(rb + 49152 + j * 8192, oimg + 2 * j * 8192, 8192, bars + 8 * MB_OA);
      *(volatile unsigned int*)&g_epoch[b] = epoch + 1;
      mbar_wait(bars + 8 * MB_ATT, 0);
      mbar_expect_tx(bars + 8 * MB_OB, 24576);
      load_w(sb + 49152, 6, bars + 8 * MB_OB);
      bulk_g2s(sb, oimg + 6 * 8192, 8192, bars + 8 * MB_OB);
      for (int j = 0; j < 4; j++) {
        mbar_expect_tx(bars + 8 * (MB_O + j), 24576);
        load_w(sb + 65536 + j * 16384, 2 * j + 1, bars + 8 * (MB_O + j));
      }
      wait4_each(&g_oflag[1][qb * 4], (epoch + 1) * 4,
                 [&](int j) { bulk_g2s(sb + 8192 + j * 8192, oimg + (2 * j + 1) * 8192, 8192, bars + 8 * (MB_O + j)); });
    }
    return;
  }

  uint32_t epoch = 0;
  if (tid == 0) epoch = *(volatile unsigned int*)&g_epoch[b];
  if (wg == 0) {
    float d[4] = {0.f, 0.f, 0.f, 0.f};
    fence_regs(d);
    mbar_wait_u(bars + 8 * MB_X, 0);
    fence_async_smem();
    const uint64_t da0 = make_desc(sb + SM_X, 16, 1024, 1);
    const uint64_t db0 = make_desc(sb + SM_WKV, 128, 128, 0);
    wg_fence();
#pragma unroll 1
    for (int kb = 0; kb < 8; kb++) {
      wg_fence();
#pragma unroll
      for (int k = 0; k < 4; k++) wgmma_ss8_tb(d, da0 + (uint64_t)(uint32_t)(kb * 512 + k * 2), db0 + (uint64_t)(uint32_t)(kb * 64 + k * 16));
    }
    wg_commit();
    wg_wait<0>();
    fence_regs(d);
    if (lane == 0) mbar_arrive(bars + 8 * MB_KVG);
    const uint32_t p0 = pack_bf16(d[0], d[1]), p1 = pack_bf16(d[2], d[3]);
    const int key0 = qb * 64 + 16 * w + rq;
    float stat;
    if (hg < 2) {
      unsigned char* dst = g_Kimg + (key0 >> 3) * 256 + hg * 128 + (key0 & 7) * 16 + q2 * 2;
      *(uint32_t*)dst = p0;
      *(uint32_t*)(dst + 256) = p1;
      float s0 = bf_lo(p0) * bf_lo(p0) + bf_hi(p0) * bf_hi(p0), s1 = bf_lo(p1) * bf_lo(p1) + bf_hi(p1) * bf_hi(p1);
      s0 += __shfl_xor_sync(~0u, s0, 1); s0 += __shfl_xor_sync(~0u, s0, 2);
      s1 += __shfl_xor_sync(~0u, s1, 1); s1 += __shfl_xor_sync(~0u, s1, 2);
      stat = fmaxf(s0, s1);
      if (!(s0 + s1 < INFINITY)) stat = INFINITY;
    } else {
      unsigned char* per = g_Vimg + (qb * 8 + 2 * w) * 272;
      uint32_t t0, t1;
      asm volatile("movmatrix.sync.aligned.m8n8.trans.b16 %0, %1;\n" : "=r"(t0) : "r"(p0));
      asm volatile("movmatrix.sync.aligned.m8n8.trans.b16 %0, %1;\n" : "=r"(t1) : "r"(p1));
      unsigned char* dst = per + (hg == 2 ? 144 : 272 + 16) + lane * 4;
      *(uint32_t*)dst = t0;
      *(uint32_t*)(dst + 272) = t1;
      if (hg == 2 && lane < 8) *(uint32_t*)(per + (lane >> 2) * 272 + (lane & 3) * 4) = 0x3F803F80u;
      stat = fmaxf(fmaxf(fabsf(bf_lo(p0)), fabsf(bf_hi(p0))), fmaxf(fabsf(bf_lo(p1)), fabsf(bf_hi(p1))));
    }
#pragma unroll
    for (int o = 16; o; o >>= 1) stat = fmaxf(stat, __shfl_xor_sync(~0u, stat, o));
    if (lane == 0) g_stat[b * 4 + w] = stat;
    bar_sync(1, 128);
    if (tid == 0) red_add_release(&g_bar);
    __syncwarp();
  } else if (wg == 1) {
    float d[64];
#pragma unroll
    for (int i = 0; i < 64; i++) d[i] = 0.f;
    fence_regs(d);
    mbar_wait_u(bars + 8 * MB_KVG, 0);
    const uint64_t da0 = make_desc(sb + SM_X, 16, 1024, 1);
#pragma unroll 1
    for (int pc = 0; pc < 8; pc++) {
      const uint32_t src = pc < 4 ? SM_RING + pc * 16384 : (pc == 4 ? SM_WQ4 : (pc < 7 ? SM_JOB + (pc - 5) * 16384 : SM_RING));
      const uint64_t db0 = make_desc(sb + src, 8192, 1024, 1);
      mbar_wait_u(bars + 8 * (MB_WQ + pc), 0);
      fence_async_smem();
      wg_fence();
#pragma unroll
      for (int k = 0; k < 4; k++) wgmma_ss128_tb(d, da0 + (uint64_t)(uint32_t)(pc * 512 + k * 2), db0 + (uint64_t)(k * 128));
      wg_commit();
      if (pc == 1) {
        wg_wait<1>();
        bar_sync(2, 128);
        if (tid == 0) {
          mbar_expect_tx(bars + 8 * (MB_WQ + 7), 16384);
          for (int nb = 0; nb < 2; nb++) tma_2d(sb + SM_RING + nb * 8192, &tm_wq, hg * 128 + nb * 64, 7 * 64, bars + 8 * (MB_WQ + 7));
        }
        __syncwarp();
      }
    }
    wg_wait<0>();
    fence_regs(d);
    bar_sync(2, 128);
    const float qs = 0.25f * 1.4426950408889634f;
    const uint32_t dst = sb + SM_Q + (16 * w + rq) * 272 + q2 * 2;
#pragma unroll
    for (int i = 0; i < 16; i++) {
      sts32(dst + i * 16, pack_bf16(d[4 * i] * qs, d[4 * i + 1] * qs));
      sts32(dst + 8 * 272 + i * 16, pack_bf16(d[4 * i + 2] * qs, d[4 * i + 3] * qs));
    }
    fence_async_smem();
    bar_sync(2, 128);
    if (tid == 0) mbar_arrive(bars + 8 * MB_QDONE);
  } else {
    if (wg == 2) {
      const uint32_t su = sb + SM_U;
      if (tid == 0) {
        mbar_wait(bars + 8 * MB_X, 0);
        mbar_expect_tx(bars + 8 * MB_UIN, 16384);
        tma_2d(su, &tm_u, qb * 16, hg * 512, bars + 8 * MB_UIN);
        tma_2d(su + 8192, &tm_u, qb * 16, hg * 512 + 256, bars + 8 * MB_UIN);
      }
      __syncwarp();
      mbar_wait_u(bars + 8 * MB_UIN, 0);
      uint32_t r[8][4];
#pragma unroll
      for (int it = 0; it < 8; it++)
        ldsm_x4_t(r[it], su + (w * 128 + it * 16 + (lane >> 4) * 8 + (lane & 7)) * 32 + ((lane >> 3) & 1) * 16);
      bar_sync(3, 128);
#pragma unroll
      for (int it = 0; it < 8; it++) {
        const uint32_t o0 = swz64(2 * (w * 128 + it * 16 + q2)), o1 = swz64(2 * (w * 128 + it * 16 + 8 + q2));
        sts32(su + rq * 1040 + o0, r[it][0]);
        sts32(su + (rq + 8) * 1040 + o0, r[it][1]);
        sts32(su + rq * 1040 + o1, r[it][2]);
        sts32(su + (rq + 8) * 1040 + o1, r[it][3]);
      }
      fence_async_smem();
      bar_sync(3, 128);
      if (w == 0) {
        if (lane < 16) {
          asm volatile("cp.async.bulk.global.shared::cta.bulk_group [%0], [%1], 1024;\n" ::"l"((uint64_t)(g_U + (size_t)(qb * 16 + lane) * 2048 + hg * 512)),
                       "r"(su + lane * 1040) : "memory");
          asm volatile("cp.async.bulk.commit_group;\ncp.async.bulk.wait_group 0;\n" ::: "memory");
        }
        __syncwarp();
        if (lane == 0) red_add_release(&g_uflag[b]);
      }
      bar_sync(3, 128);
      sts128(su + w * U_STRIDE + lane * 16, 0, 0, 0, 0);
      fence_async_smem();
      bar_sync(3, 128);
      if (tid == 0) mbar_arrive(bars + 8 * MB_UFREE);
    } else {
      if (tid == 0) {
        mbar_wait(bars + 8 * MB_QDONE, 0);
        wait_counter(&g_bar, (epoch + 1) * NCTA);
        load_kv_chunk(sb, 0);
        load_kv_chunk(sb, 1);
        for (int nb = 0; nb < 2; nb++)
          asm volatile("cp.async.bulk.prefetch.tensor.2d.L2.global.tile [%0, {%1, %2}];\n" ::"l"((uint64_t)&tm_wo), "r"(hg * 128 + nb * 64),
                       "r"((qb & 7) * 64) : "memory");
      }
      __syncwarp();
    }
  }
  float kmax2 = 0.f;
  bool v_ok = true;
  mbar_wait_u(bars + 8 * MB_QDONE, 0);
#pragma unroll 1
  for (int t = 0; t < 2; t++) {
    const int hl = wg + 4 * t;
    uint32_t q[4];
    ldsm_x4(q, sb + SM_Q + (16 * w + (lane & 15)) * 272 + hl * 32 + (lane >> 4) * 16);
    float n0 = bf_lo(q[0]) * bf_lo(q[0]) + bf_hi(q[0]) * bf_hi(q[0]) + bf_lo(q[2]) * bf_lo(q[2]) + bf_hi(q[2]) * bf_hi(q[2]);
    float n1 = bf_lo(q[1]) * bf_lo(q[1]) + bf_hi(q[1]) * bf_hi(q[1]) + bf_lo(q[3]) * bf_lo(q[3]) + bf_hi(q[3]) * bf_hi(q[3]);
    n0 += __shfl_xor_sync(~0u, n0, 1); n0 += __shfl_xor_sync(~0u, n0, 2);
    n1 += __shfl_xor_sync(~0u, n1, 1); n1 += __shfl_xor_sync(~0u, n1, 2);
    if (t == 0) {
      mbar_wait_u(bars + 8 * MB_KV0, 0);
      float ka, kb, vm = 0.f;
#pragma unroll
      for (int i = 0; i < 4; i++) {
        uint32_t st[4];
        lds128(st, sb + SM_STAT + lane * 64 + i * 16);
        const float mx = fmaxf(fmaxf(__uint_as_float(st[0]), __uint_as_float(st[1])), fmaxf(__uint_as_float(st[2]), __uint_as_float(st[3])));
        if (i == 0) ka = mx; else if (i == 1) kb = mx; else vm = fmaxf(vm, mx);
      }
      ka = __uint_as_float(__reduce_max_sync(~0u, __float_as_uint(ka)));
      kb = __uint_as_float(__reduce_max_sync(~0u, __float_as_uint(kb)));
      vm = __uint_as_float(__reduce_max_sync(~0u, __float_as_uint(vm)));
      kmax2 = ka + kb;
      v_ok = (vm < 1.0e9f) && (vm > 1.0e-9f || vm == 0.f);
    }
    const bool unsafe = !(n0 * kmax2 <= 6400.f) || !(n1 * kmax2 <= 6400.f) || !v_ok;
    const bool fast = !__any_sync(0xffffffffu, bar_red_or(1 + wg, 128, unsafe));
    float o[12];
    if (fast) {
      attn_tile<true>(o, q, sb, t == 0, 0.f, 0.f);
    } else {
      float m0, m1;
      attn_rowmax(q, sb, t == 0, m0, m1);
      float o2[12];
      attn_tile<false>(o2, q, sb, false, m0, m1);
#pragma unroll
      for (int i = 0; i < 12; i++) o[i] = opaque_copy(o2[i]);
    }
    const float l0 = __shfl_sync(~0u, o[0], lane & ~3), l1 = __shfl_sync(~0u, o[2], lane & ~3);
    const float i0 = __frcp_rn(l0), i1 = __frcp_rn(l1);
    const int col = (hg * 8 + hl) * 16;
    const int kb = col >> 6, c0 = (col & 63) >> 3;
    const int r0 = 16 * w + rq;
    unsigned char* img = g_Oimg + qb * 65536 + kb * 8192;
    *(uint32_t*)(img + r0 * 128 + ((c0 ^ (r0 & 7)) << 4) + q2 * 2) = pack_bf16(o[4] * i0, o[5] * i0);
    *(uint32_t*)(img + r0 * 128 + (((c0 + 1) ^ (r0 & 7)) << 4) + q2 * 2) = pack_bf16(o[8] * i0, o[9] * i0);
    *(uint32_t*)(img + (r0 + 8) * 128 + ((c0 ^ (r0 & 7)) << 4) + q2 * 2) = pack_bf16(o[6] * i1, o[7] * i1);
    *(uint32_t*)(img + (r0 + 8) * 128 + (((c0 + 1) ^ (r0 & 7)) << 4) + q2 * 2) = pack_bf16(o[10] * i1, o[11] * i1);
    if (t == 0) {
      __syncwarp();
      if (lane == 0) mbar_arrive(bars + 8 * MB_EARLY);
    }
  }
  fence_async_smem();
  bar_sync(1 + wg, 128);
  if (tid == 0) {
    red_add_release(&g_oflag[1][b]);
    mbar_arrive(bars + 8 * MB_ATT);
  }
  if (wg == 1) {
    const uint32_t rb = sb + SM_JOB;
    float d[64];
#pragma unroll
    for (int i = 0; i < 64; i++) d[i] = 0.f;
    fence_regs(d);
#pragma unroll 1
    for (int i = 0; i < 8; i++) {
      const uint32_t sa = i < 3 ? rb + 49152 + i * 8192 : sb + (i - 3) * 8192;
      const uint32_t sw = i < 3 ? rb + i * 16384 : sb + 49152 + (i - 3) * 16384;
      mbar_wait_u(bars + 8 * (i < 3 ? MB_OA : MB_OB + (i - 3)), 0);
      const uint64_t da = make_desc(sa, 16, 1024, 1), db = make_desc(sw, 8192, 1024, 1);
      wg_fence();
#pragma unroll
      for (int k = 0; k < 4; k++) wgmma_ss128_tb(d, da + (uint64_t)(k * 2), db + (uint64_t)(k * 128));
      wg_commit();
    }
    wg_wait<0>();
    fence_regs(d);
    const uint32_t st = sb + 40960;
    bar_sync(2, 128);
    const int r0 = 16 * w + rq;
#pragma unroll
    for (int i = 0; i < 16; i++) {
      const uint32_t a0 = st + (i >> 3) * 8192 + r0 * 128 + (((i & 7) ^ (r0 & 7)) << 4) + q2 * 2;
      sts32(a0, pack_bf16(d[4 * i], d[4 * i + 1]));
      sts32(a0 + 1024, pack_bf16(d[4 * i + 2], d[4 * i + 3]));
    }
    fence_async_smem();
    bar_sync(2, 128);
    if (tid == 0) {
      tma_store_issue(&tm_out, st, hg * 128, qb * 64);
      tma_store_2d(&tm_out, st + 8192, hg * 128 + 64, qb * 64);
    }
  } else if (wg == 2) {
    const uint32_t gb = sb + SM_Q;
    if (w == 0) {
      if (lane == 0) {
        mbar_wait(bars + 8 * MB_ATT, 0);
        mbar_expect_tx(bars + 8 * MB_Y, 16384);
        wait4_each(&g_yflag[qb * 4], epoch + 1, [](int) {});
      }
      __syncwarp();
      if (lane < 16) bulk_g2s(gb + lane * 1040, g_Y + (size_t)(qb * 16 + lane) * 2048 + hg * 512, 1024, bars + 8 * MB_Y);
    }
    mbar_wait_u(bars + 8 * MB_Y, 0);
    uint32_t r[8][4];
#pragma unroll
    for (int it = 0; it < 8; it++) ldsm_x4_t(r[it], gb + (lane & 15) * 1040 + (w * 128 + it * 16 + (lane >> 4) * 8) * 2);
    bar_sync(3, 128);
#pragma unroll
    for (int it = 0; it < 8; it++) {
      const uint32_t dst = gb + (w * 128 + it * 16 + rq) * 32 + q2 * 2;
      sts32(dst, r[it][0]); sts32(dst + 16, r[it][1]); sts32(dst + 256, r[it][2]); sts32(dst + 256 + 16, r[it][3]);
    }
    fence_async_smem();
    bar_sync(3, 128);
    if (tid == 0) {
      tma_store_issue(&tm_outb, gb, 512 + qb * 16, hg * 512);
      tma_store_2d(&tm_outb, gb + 8192, 512 + qb * 16, hg * 512 + 256);
    }
  }
}

typedef CUresult (*EncodeFn)(CUtensorMap*, CUtensorMapDataType, cuuint32_t, void*, const cuuint64_t*, const cuuint64_t*, const cuuint32_t*,
                             const cuuint32_t*, CUtensorMapInterleave, CUtensorMapSwizzle, CUtensorMapL2promotion, CUtensorMapFloatOOBfill);

void make_map(EncodeFn fn, CUtensorMap* tm, const void* ptr, uint64_t rows, uint64_t cols, uint32_t box_rows, uint32_t box_cols, bool swz) {
  cuuint64_t dims[2] = {cols, rows};
  cuuint64_t strides[1] = {cols * 2};
  cuuint32_t box[2] = {box_cols, box_rows};
  cuuint32_t es[2] = {1, 1};
  fn(tm, CU_TENSOR_MAP_DATA_TYPE_BFLOAT16, 2, const_cast<void*>(ptr), dims, strides, box, es, CU_TENSOR_MAP_INTERLEAVE_NONE,
     swz ? CU_TENSOR_MAP_SWIZZLE_128B : CU_TENSOR_MAP_SWIZZLE_NONE, CU_TENSOR_MAP_L2_PROMOTION_L2_128B, CU_TENSOR_MAP_FLOAT_OOB_FILL_NONE);
}

}

extern "C" void kernel_launch(void* const* d_in, const int* in_sizes, int n_in, void* d_out, int out_size) {
  static EncodeFn encode = nullptr;
  if (!encode) {
    void* fn = nullptr;
    cudaDriverEntryPointQueryResult st;
    cudaGetDriverEntryPoint("cuTensorMapEncodeTiled", &fn, cudaEnableDefault, &st);
    encode = (EncodeFn)fn;
    cudaFuncSetAttribute(fused_kernel, cudaFuncAttributeMaxDynamicSharedMemorySize, SM_TOTAL);
  }
  CUtensorMap tm_wq, tm_wo, tm_out, tm_outb, tm_u;
  make_map(encode, &tm_wq, d_in[1], 512, 512, 64, 64, true);
  make_map(encode, &tm_out, d_out, 2048, 1024, 64, 64, true);
  make_map(encode, &tm_outb, d_out, 2048, 1024, 256, 16, false);
  make_map(encode, &tm_u, d_in[5], 2048, 512, 256, 16, false);
  make_map(encode, &tm_wo, d_in[4], 512, 512, 64, 64, true);
  Params P;
  P.x = (const __nv_bfloat16*)d_in[0];
  P.wq = (const __nv_bfloat16*)d_in[1];
  P.wk = (const __nv_bfloat16*)d_in[2];
  P.wv = (const __nv_bfloat16*)d_in[3];
  P.log_A_real = (const __nv_bfloat16*)d_in[6];
  P.A_imag = (const __nv_bfloat16*)d_in[7];
  P.C_real = (const __nv_bfloat16*)d_in[8];
  P.C_imag = (const __nv_bfloat16*)d_in[9];
  P.log_dt = (const __nv_bfloat16*)d_in[10];
  P.D_skip = (const __nv_bfloat16*)d_in[11];
  P.out = (__nv_bfloat16*)d_out;
  fused_kernel<<<NCTA, NTHREADS, SM_TOTAL>>>(tm_wq, tm_wo, tm_out, tm_outb, tm_u, P);
}
```
